```python
import torch

def _softmax(x, axis=-1):
    return torch.softmax(x, dim=axis)
def _gelu(x):
    return torch.nn.functional.gelu(x, approximate="tanh")
def _silu(x):
    return torch.nn.functional.silu(x)
def _sigmoid(x):
    return torch.sigmoid(x)
def _layernorm(x, axis=-1, eps=1e-5):
    m = x.mean(dim=axis, keepdim=True)
    v = x.var(dim=axis, keepdim=True, unbiased=False)
    return (x - m) / torch.sqrt(v + eps)
def _scatter_add(tgt, idx, src, axis=0):
    return tgt.clone().index_add_(axis, idx, src)
def _segment_sum(src, seg, n):
    out = torch.zeros((n,) + src.shape[1:], dtype=src.dtype)
    return out.index_add_(0, seg, src)
def _pad(x, pw):
    flat = tuple(v for pair in reversed(pw) for v in pair)
    return torch.nn.functional.pad(x, flat)

kernel_name = 'gated_mix__linear_attn_block__sliding_block__prompt'

def setup_inputs():

    _w = (lambda a: (lambda t: t.to(torch.bfloat16) if t.is_floating_point() else t)(torch.as_tensor(a)))
    def _A_setup():
        B, S, D = 1, 2048, 512
        return {
            "x": _w((lambda *s: torch.randn(*s, dtype=torch.bfloat16) * 0.05)(B, S, D)),
            "wqkv": _w((lambda *s: torch.randn(*s, dtype=torch.bfloat16) * 1.6)(D, 3 * D)),
            "wo": _w((lambda *s: torch.randn(*s, dtype=torch.bfloat16) * 1.6)(D, D)),
        }
    _A_in = _A_setup()

    def _B_setup():
        B, S, D = 1, 2048, 512
        return {
            "x": _w((lambda *s: torch.randn(*s, dtype=torch.bfloat16) * 0.05)(B, S, D)),
            "wqkv": _w((lambda *s: torch.randn(*s, dtype=torch.bfloat16) * 1.6)(D, 3 * D)),
            "wo": _w((lambda *s: torch.randn(*s, dtype=torch.bfloat16) * 0.05)(D, D)),
        }
    _B_in = _B_setup()

    return {
        "A_x": _A_in["x"],
        "A_wqkv": _A_in["wqkv"],
        "A_wo": _A_in["wo"],
        "B_x": _B_in["x"],
        "B_wqkv": _B_in["wqkv"],
        "B_wo": _B_in["wo"],
        "gate_w": _w((lambda *s: torch.randn(*s, dtype=torch.bfloat16) * 0.05)(512) * 16.0),
    }

def reference(A_x, A_wqkv, A_wo, B_x, B_wqkv, B_wo, gate_w):
    def _A_ref(x, wqkv, wo):
        B, S, D = x.shape
        H = 32; Dh = D // H
        qkv = (lambda x, *d: x.permute(*d))((x @ wqkv).reshape(B, S, 3, H, Dh), 2, 0, 3, 1, 4)
        q, k, v = qkv[0], qkv[1], qkv[2]
        phi = lambda t: torch.where(t > 0, t + 1, torch.exp(t)) + 1e-6
        pq, pk = phi(q), phi(k)
        kv = torch.einsum("bhsd,bhse->bhde", pk, v)
        z = torch.einsum("bhsd->bhd", pk)
        num = torch.einsum("bhqd,bhde->bhqe", pq, kv)
        den = torch.einsum("bhqd,bhd->bhq", pq, z)[..., None] + 1e-6
        o = num / den
        return (lambda x, *d: x.permute(*d))(o, 0, 2, 1, 3).reshape(B, S, D) @ wo

    def _B_ref(x, wqkv, wo):
        B, S, D = x.shape
        H = 32; Dh = D // H; W = 256
        qkv = (lambda x, *d: x.permute(*d))((x @ wqkv).reshape(B, S, 3, H, Dh), 2, 0, 3, 1, 4)
        q, k, v = qkv[0], qkv[1], qkv[2]
        scores = torch.einsum("bhqd,bhkd->bhqk", q, k) * (Dh ** -0.5)
        idx = torch.arange(S)
        mask = (idx[:, None] - idx[None, :] >= 0) & (idx[:, None] - idx[None, :] < W)
        scores = torch.where(mask[None, None], scores, -1e9)
        p = _softmax(scores, axis=-1)
        o = torch.einsum("bhqk,bhkd->bhqd", p, v)
        return (lambda x, *d: x.permute(*d))(o, 0, 2, 1, 3).reshape(B, S, D) @ wo

    x = A_x
    g = _sigmoid((x * gate_w).sum(-1, keepdims=True))
    a = _A_ref(x, A_wqkv, A_wo)
    b = _B_ref(x, B_wqkv, B_wo)
    return g * a + (1 - g) * b
```

```cpp
#include <cuda_runtime.h>
#include <cuda_bf16.h>
#include <cuda.h>
#include <stdint.h>

template <int TA, int TB>
__device__ __forceinline__ void wg_ss192(float (&d)[96], uint64_t da, uint64_t db, int sd) {
  asm volatile("{\n.reg .pred p;\nsetp.ne.b32 p, %98, 0;\n"
      "wgmma.mma_async.sync.aligned.m64n192k16.f32.bf16.bf16 {%0, %1, %2, %3, %4, %5, %6, %7, %8, %9, %10, %11, %12, %13, %14, %15, %16, %17, %18, %19, %20, %21, "
      "%22, %23, %24, %25, %26, %27, %28, %29, %30, %31, %32, %33, %34, %35, %36, %37, %38, %39, %40, %41, "
      "%42, %43, %44, %45, %46, %47, %48, %49, %50, %51, %52, %53, %54, %55, %56, %57, %58, %59, %60, %61, "
      "%62, %63, %64, %65, %66, %67, %68, %69, %70, %71, %72, %73, %74, %75, %76, %77, %78, %79, %80, %81, "
      "%82, %83, %84, %85, %86, %87, %88, %89, %90, %91, %92, %93, %94, %95}, "
      "%96, %97, p, 1, 1, %99, %100;\n}\n"
      : "+f"(d[0]), "+f"(d[1]), "+f"(d[2]), "+f"(d[3]), "+f"(d[4]), "+f"(d[5]), "+f"(d[6]), "+f"(d[7]), "+f"(d[8]),
      "+f"(d[9]), "+f"(d[10]), "+f"(d[11]), "+f"(d[12]), "+f"(d[13]), "+f"(d[14]), "+f"(d[15]), "+f"(d[16]),
      "+f"(d[17]), "+f"(d[18]), "+f"(d[19]), "+f"(d[20]), "+f"(d[21]), "+f"(d[22]), "+f"(d[23]), "+f"(d[24]),
      "+f"(d[25]), "+f"(d[26]), "+f"(d[27]), "+f"(d[28]), "+f"(d[29]), "+f"(d[30]), "+f"(d[31]), "+f"(d[32]),
      "+f"(d[33]), "+f"(d[34]), "+f"(d[35]), "+f"(d[36]), "+f"(d[37]), "+f"(d[38]), "+f"(d[39]), "+f"(d[40]),
      "+f"(d[41]), "+f"(d[42]), "+f"(d[43]), "+f"(d[44]), "+f"(d[45]), "+f"(d[46]), "+f"(d[47]), "+f"(d[48]),
      "+f"(d[49]), "+f"(d[50]), "+f"(d[51]), "+f"(d[52]), "+f"(d[53]), "+f"(d[54]), "+f"(d[55]), "+f"(d[56]),
      "+f"(d[57]), "+f"(d[58]), "+f"(d[59]), "+f"(d[60]), "+f"(d[61]), "+f"(d[62]), "+f"(d[63]), "+f"(d[64]),
      "+f"(d[65]), "+f"(d[66]), "+f"(d[67]), "+f"(d[68]), "+f"(d[69]), "+f"(d[70]), "+f"(d[71]), "+f"(d[72]),
      "+f"(d[73]), "+f"(d[74]), "+f"(d[75]), "+f"(d[76]), "+f"(d[77]), "+f"(d[78]), "+f"(d[79]), "+f"(d[80]),
      "+f"(d[81]), "+f"(d[82]), "+f"(d[83]), "+f"(d[84]), "+f"(d[85]), "+f"(d[86]), "+f"(d[87]), "+f"(d[88]),
      "+f"(d[89]), "+f"(d[90]), "+f"(d[91]), "+f"(d[92]), "+f"(d[93]), "+f"(d[94]), "+f"(d[95])
      : "l"(da), "l"(db), "r"(sd), "n"(TA), "n"(TB));
}
template <int TA, int TB>
__device__ __forceinline__ void wg_ss128(float (&d)[64], uint64_t da, uint64_t db, int sd) {
  asm volatile("{\n.reg .pred p;\nsetp.ne.b32 p, %66, 0;\n"
      "wgmma.mma_async.sync.aligned.m64n128k16.f32.bf16.bf16 {%0, %1, %2, %3, %4, %5, %6, %7, %8, %9, %10, %11, %12, %13, %14, %15, %16, %17, %18, %19, %20, %21, "
      "%22, %23, %24, %25, %26, %27, %28, %29, %30, %31, %32, %33, %34, %35, %36, %37, %38, %39, %40, %41, "
      "%42, %43, %44, %45, %46, %47, %48, %49, %50, %51, %52, %53, %54, %55, %56, %57, %58, %59, %60, %61, "
      "%62, %63}, "
      "%64, %65, p, 1, 1, %67, %68;\n}\n"
      : "+f"(d[0]), "+f"(d[1]), "+f"(d[2]), "+f"(d[3]), "+f"(d[4]), "+f"(d[5]), "+f"(d[6]), "+f"(d[7]), "+f"(d[8]),
      "+f"(d[9]), "+f"(d[10]), "+f"(d[11]), "+f"(d[12]), "+f"(d[13]), "+f"(d[14]), "+f"(d[15]), "+f"(d[16]),
      "+f"(d[17]), "+f"(d[18]), "+f"(d[19]), "+f"(d[20]), "+f"(d[21]), "+f"(d[22]), "+f"(d[23]), "+f"(d[24]),
      "+f"(d[25]), "+f"(d[26]), "+f"(d[27]), "+f"(d[28]), "+f"(d[29]), "+f"(d[30]), "+f"(d[31]), "+f"(d[32]),
      "+f"(d[33]), "+f"(d[34]), "+f"(d[35]), "+f"(d[36]), "+f"(d[37]), "+f"(d[38]), "+f"(d[39]), "+f"(d[40]),
      "+f"(d[41]), "+f"(d[42]), "+f"(d[43]), "+f"(d[44]), "+f"(d[45]), "+f"(d[46]), "+f"(d[47]), "+f"(d[48]),
      "+f"(d[49]), "+f"(d[50]), "+f"(d[51]), "+f"(d[52]), "+f"(d[53]), "+f"(d[54]), "+f"(d[55]), "+f"(d[56]),
      "+f"(d[57]), "+f"(d[58]), "+f"(d[59]), "+f"(d[60]), "+f"(d[61]), "+f"(d[62]), "+f"(d[63])
      : "l"(da), "l"(db), "r"(sd), "n"(TA), "n"(TB));
}
template <int TA, int TB>
__device__ __forceinline__ void wg_ss64(float (&d)[32], uint64_t da, uint64_t db, int sd) {
  asm volatile("{\n.reg .pred p;\nsetp.ne.b32 p, %34, 0;\n"
      "wgmma.mma_async.sync.aligned.m64n64k16.f32.bf16.bf16 {%0, %1, %2, %3, %4, %5, %6, %7, %8, %9, %10, %11, %12, %13, %14, %15, %16, %17, %18, %19, %20, %21, "
      "%22, %23, %24, %25, %26, %27, %28, %29, %30, %31}, "
      "%32, %33, p, 1, 1, %35, %36;\n}\n"
      : "+f"(d[0]), "+f"(d[1]), "+f"(d[2]), "+f"(d[3]), "+f"(d[4]), "+f"(d[5]), "+f"(d[6]), "+f"(d[7]), "+f"(d[8]),
      "+f"(d[9]), "+f"(d[10]), "+f"(d[11]), "+f"(d[12]), "+f"(d[13]), "+f"(d[14]), "+f"(d[15]), "+f"(d[16]),
      "+f"(d[17]), "+f"(d[18]), "+f"(d[19]), "+f"(d[20]), "+f"(d[21]), "+f"(d[22]), "+f"(d[23]), "+f"(d[24]),
      "+f"(d[25]), "+f"(d[26]), "+f"(d[27]), "+f"(d[28]), "+f"(d[29]), "+f"(d[30]), "+f"(d[31])
      : "l"(da), "l"(db), "r"(sd), "n"(TA), "n"(TB));
}
template <int TA, int TB>
__device__ __forceinline__ void wg_ss8(float (&d)[4], uint64_t da, uint64_t db, int sd) {
  asm volatile("{\n.reg .pred p;\nsetp.ne.b32 p, %6, 0;\n"
      "wgmma.mma_async.sync.aligned.m64n8k16.f32.bf16.bf16 {%0, %1, %2, %3}, "
      "%4, %5, p, 1, 1, %7, %8;\n}\n"
      : "+f"(d[0]), "+f"(d[1]), "+f"(d[2]), "+f"(d[3])
      : "l"(da), "l"(db), "r"(sd), "n"(TA), "n"(TB));
}
template <int TB>
__device__ __forceinline__ void wg_rs24(float (&d)[12], uint32_t a0, uint32_t a1, uint32_t a2, uint32_t a3, uint64_t db, int sd) {
  asm volatile("{\n.reg .pred p;\nsetp.ne.b32 p, %17, 0;\n"
      "wgmma.mma_async.sync.aligned.m64n24k16.f32.bf16.bf16 {%0, %1, %2, %3, %4, %5, %6, %7, %8, %9, %10, %11}, "
      "{%12, %13, %14, %15}, %16, p, 1, 1, %18;\n}\n"
      : "+f"(d[0]), "+f"(d[1]), "+f"(d[2]), "+f"(d[3]), "+f"(d[4]), "+f"(d[5]), "+f"(d[6]), "+f"(d[7]), "+f"(d[8]),
      "+f"(d[9]), "+f"(d[10]), "+f"(d[11])
      : "r"(a0), "r"(a1), "r"(a2), "r"(a3), "l"(db), "r"(sd), "n"(TB));
}

#define MAP 2
#define BUSYW 1
#define BUSYO 0
#define LATE 14
#define NFAST 5
namespace {

constexpr uint32_t GSLOT = 40960;
constexpr uint32_t OSLOT = 24576;
constexpr uint32_t STGOFF = 3 * OSLOT;
constexpr uint32_t KVOFF = 122880;
constexpr uint32_t ONES = KVOFF + 12 * 8192;
constexpr uint32_t MISC = ONES + 1024;
constexpr uint32_t BARS = MISC;
constexpr uint32_t TAGOFF = MISC + 624;
constexpr uint32_t PMASKOFF = MISC + 620;
constexpr uint32_t ORDOFF = MISC + 628;
constexpr uint32_t GSOFF = MISC + 640;
constexpr uint32_t QOFF = GSOFF + 512;
constexpr uint32_t KVZOFF = KVOFF + 8 * 8192;
constexpr uint32_t GWOFF = QOFF;
constexpr uint32_t SMEM_BYTES = QOFF + 8192;
static_assert(SMEM_BYTES <= 232448, "smem");

enum {
  B_FULLG = 0  , B_EMPTYG = 5  , B_HALO = 10  , B_FULLO = 18  , B_FREEO = 34  , B_STGFREE = 43, B_GATE = 44, B_OADONE = 45,
  B_Q3FULL = 46  , B_OBDONE = 48  , B_ATTN = 52, B_ADONE = 53, B_LLRDY = 54, B_TAG = 55, B_PARTRDY = 56, B_ASTART = 57, B_LLO = 58, B_SEQ = 59  , B_ISSUED = 67, B_COUNT = 68
};

constexpr float kLog2e = 1.4426950408889634f;
constexpr float kScaleLog2 = 0.25f * 1.4426950408889634f;

__device__ __align__(1024) uint8_t g_kvx[16 * 8 * 32768];
__device__ __align__(1024) uint4 g_ll[2 * 128 * 512];
__device__ __align__(1024) uint32_t g_lp[2 * 128 * 576];
__device__ __align__(1024) uint4 g_q[128 * 4 * 256];
__device__ __align__(1024) uint8_t g_o[16 * 14 * 16384];
__device__ __align__(1024) uint4 g_o2[2 * 16 * 2 * 1024];
__device__ __align__(128) uint32_t g_fOA[16 * 32];
__device__ __align__(128) uint32_t g_fKV[8 * 16 * 2];
__device__ __align__(128) uint32_t g_fOB[16 * 32];
__device__ uint32_t g_ticket;
#define TL(slot) do {} while (0)
#define TLG(slot) do {} while (0)

__device__ __forceinline__ uint32_t clock32() { uint32_t c; asm volatile("mov.u32 %0, %%clock;" : "=r"(c)); return c; }
__device__ __forceinline__ void mbar_init(uint32_t b, int c) { asm volatile("mbarrier.init.shared::cta.b64 [%0], %1;" ::"r"(b), "r"(c)); }
#define ONE(ins) "{\n.reg .pred e;\nelect.sync _|e, 0xffffffff;\n@e " ins "\n}"
__device__ __forceinline__ void mbar_expect(uint32_t b, int bytes) { asm volatile(ONE("mbarrier.arrive.expect_tx.shared::cta.b64 _, [%0], %1;") ::"r"(b), "r"(bytes) : "memory"); }
__device__ __forceinline__ bool mbar_test(uint32_t b, uint32_t ph) {
  uint32_t ok;
  asm volatile("{\n.reg .pred p;\nmbarrier.test_wait.parity.shared::cta.b64 p, [%1], %2;\nselp.u32 %0, 1, 0, p;\n}" : "=r"(ok) : "r"(b), "r"(ph) : "memory");
  return ok;
}
__device__ __forceinline__ void mbar_wait(uint32_t b, uint32_t ph) {
  asm volatile("{\n.reg .pred p;\n.reg .u32 n;\nmov.u32 n, 0;\nW:\nmbarrier.try_wait.parity.shared::cta.b64 p, [%0], %1;\n"
               "add.u32 n, n, 1;\nsetp.lt.and.u32 p, n, 16384, !p;\n@p bra W;\n}" ::"r"(b), "r"(ph) : "memory");
}
__device__ __forceinline__ void mbar_wait_hot(uint32_t b, uint32_t ph) {
  asm volatile("{\n.reg .pred p;\n.reg .u32 n;\nmbarrier.try_wait.parity.shared::cta.b64 p, [%0], %1;\n@p bra D;\nmov.u32 n, 0;\nW:\n"
               "mbarrier.try_wait.parity.shared::cta.b64 p, [%0], %1;\nadd.u32 n, n, 1;\nsetp.lt.and.u32 p, n, 16384, !p;\n@p bra W;\nD:\n}" ::"r"(b), "r"(ph) : "memory");
}
__device__ __forceinline__ uint32_t ld_rlx(const uint32_t* p) { uint32_t v; asm volatile("ld.relaxed.gpu.global.u32 %0, [%1];" : "=r"(v) : "l"(p) : "memory"); return v; }
__device__ __forceinline__ void st_rel(uint32_t* p, uint32_t v) { asm volatile(ONE("st.release.gpu.global.u32 [%0], %1;") ::"l"(p), "r"(v) : "memory"); }
__device__ __forceinline__ void st_rlx(uint32_t* p, uint32_t v) { asm volatile("st.relaxed.gpu.global.u32 [%0], %1;" ::"l"(p), "r"(v) : "memory"); }
__device__ __forceinline__ void fence_async_smem() { asm volatile("fence.proxy.async.shared::cta;" ::: "memory"); }
__device__ __forceinline__ void fence_async_glob() { asm volatile("fence.proxy.async.global;" ::: "memory"); }
template <int ID, int N> __device__ __forceinline__ void bar_sync() { asm volatile("bar.sync %0, %1;" ::"n"(ID), "n"(N) : "memory"); }
__device__ __forceinline__ bool bar_red_or(int id, int n, bool v) {
  uint32_t r;
  asm volatile("{\n.reg .pred p, q;\nsetp.ne.u32 p, %3, 0;\nbar.red.or.pred q, %1, %2, p;\nselp.u32 %0, 1, 0, q;\n}" : "=r"(r) : "r"(id), "r"(n), "r"((uint32_t)v) : "memory");
  return r;
}
__device__ __forceinline__ void tma2d(uint32_t dst, const CUtensorMap* tm, uint32_t bar, int c0, int c1) {
  asm volatile(ONE("cp.async.bulk.tensor.2d.shared::cluster.global.mbarrier::complete_tx::bytes [%0], [%1, {%3, %4}], [%2];") ::"r"(dst), "l"(tm), "r"(bar), "r"(c0), "r"(c1) : "memory");
}
__device__ __forceinline__ void tma3d(uint32_t dst, const CUtensorMap* tm, uint32_t bar, int c0, int c1, int c2) {
  asm volatile(ONE("cp.async.bulk.tensor.3d.shared::cluster.global.mbarrier::complete_tx::bytes [%0], [%1, {%3, %4, %5}], [%2];") ::"r"(dst), "l"(tm), "r"(bar), "r"(c0), "r"(c1), "r"(c2) : "memory");
}
__device__ __forceinline__ void tma5d(uint32_t dst, const CUtensorMap* tm, uint32_t bar, int c0, int c1, int c2, int c3, int c4) {
  asm volatile(ONE("cp.async.bulk.tensor.5d.shared::cluster.global.mbarrier::complete_tx::bytes [%0], [%1, {%3, %4, %5, %6, %7}], [%2];") ::"r"(dst), "l"(tm), "r"(bar), "r"(c0), "r"(c1), "r"(c2), "r"(c3), "r"(c4) : "memory");
}
__device__ __forceinline__ void tma2d_store(const CUtensorMap* tm, uint32_t src, int c0, int c1) {
  asm volatile(ONE("cp.async.bulk.tensor.2d.global.shared::cta.bulk_group [%0, {%2, %3}], [%1];") ::"l"(tm), "r"(src), "r"(c0), "r"(c1) : "memory");
}
__device__ __forceinline__ void bulk_load(uint32_t dst, const void* src, int bytes, uint32_t bar) {
  asm volatile(ONE("cp.async.bulk.shared::cluster.global.mbarrier::complete_tx::bytes [%0], [%1], %2, [%3];") ::"r"(dst), "l"(src), "r"(bytes), "r"(bar) : "memory");
}
__device__ __forceinline__ void bulk_store(void* dst, uint32_t src, int bytes) {
  asm volatile(ONE("cp.async.bulk.global.shared::cta.bulk_group [%0], [%1], %2;") ::"l"(dst), "r"(src), "r"(bytes) : "memory");
}
__device__ __forceinline__ void bulk_commit() { asm volatile(ONE("cp.async.bulk.commit_group;") ::: "memory"); }
template <int N> __device__ __forceinline__ void bulk_wait() { asm volatile(ONE("cp.async.bulk.wait_group %0;") ::"n"(N) : "memory"); }
template <int N> __device__ __forceinline__ void bulk_wait_read() { asm volatile(ONE("cp.async.bulk.wait_group.read %0;") ::"n"(N) : "memory"); }
__device__ __forceinline__ void prefetch_tm(const CUtensorMap* tm) { asm volatile(ONE("prefetch.tensormap [%0];") ::"l"(tm) : "memory"); }
__device__ __forceinline__ void wg_fence() { asm volatile("wgmma.fence.sync.aligned;" ::: "memory"); }
__device__ __forceinline__ void wg_commit() { asm volatile("wgmma.commit_group.sync.aligned;" ::: "memory"); }
template <int N> __device__ __forceinline__ void wg_wait() { asm volatile("wgmma.wait_group.sync.aligned %0;" ::"n"(N) : "memory"); }
template <int N> __device__ __forceinline__ void pin(float (&d)[N]) {
#pragma unroll
  for (int i = 0; i < N; i++) asm volatile("" : "+f"(d[i])::"memory");
}
template <int N> __device__ __forceinline__ void pin(uint32_t (&d)[N]) {
#pragma unroll
  for (int i = 0; i < N; i++) asm volatile("" : "+r"(d[i])::"memory");
}
template <int N> __device__ __forceinline__ void pin(uint4 (&d)[N]) {
#pragma unroll
  for (int i = 0; i < N; i++) asm volatile("" : "+r"(d[i].x), "+r"(d[i].y), "+r"(d[i].z), "+r"(d[i].w)::"memory");
}
__device__ __forceinline__ uint32_t pack2(float lo, float hi) { uint32_t d; asm("cvt.rn.bf16x2.f32 %0, %1, %2;" : "=r"(d) : "f"(hi), "f"(lo)); return d; }
__device__ __forceinline__ float ex2(float x) { float y; asm("ex2.approx.ftz.f32 %0, %1;" : "=f"(y) : "f"(x)); return y; }
__device__ __forceinline__ void stsm4(uint32_t a, uint32_t r0, uint32_t r1, uint32_t r2, uint32_t r3) {
  asm volatile("stmatrix.sync.aligned.m8n8.x4.shared.b16 [%0], {%1, %2, %3, %4};" ::"r"(a), "r"(r0), "r"(r1), "r"(r2), "r"(r3) : "memory");
}
__device__ __forceinline__ float rcp(float x) { float y; asm("rcp.approx.ftz.f32 %0, %1;" : "=f"(y) : "f"(x)); return y; }
__device__ __forceinline__ void st_pair(uint8_t* p, uint2 a, uint2 b, bool c) {
  asm volatile("{\n.reg .pred p;\nsetp.ne.u32 p, %5, 0;\n@p st.global.v2.u32 [%0], {%1, %2};\n@p st.global.v2.u32 [%0 + 256], {%3, %4};\n}"
               ::"l"(p), "r"(a.x), "r"(a.y), "r"(b.x), "r"(b.y), "r"((uint32_t)c) : "memory");
}
__device__ __forceinline__ void st_pair_ll(uint8_t* p, uint2 a, uint2 b, bool c) {
  asm volatile("{\n.reg .pred p;\nsetp.ne.u32 p, %5, 0;\n@p st.relaxed.gpu.global.v2.u32 [%0], {%1, %2};\n@p st.relaxed.gpu.global.v2.u32 [%0 + 256], {%3, %4};\n}"
               ::"l"(p), "r"(a.x ^ 0xFFFF0000u), "r"(a.y ^ 0xFFFF0000u), "r"(b.x ^ 0xFFFF0000u), "r"(b.y ^ 0xFFFF0000u), "r"((uint32_t)c) : "memory");
}
__device__ __forceinline__ void mbar_arrive_if(uint32_t b, bool c) {
  asm volatile("{\n.reg .pred p;\nsetp.ne.u32 p, %1, 0;\n@p mbarrier.arrive.shared::cta.b64 _, [%0];\n}" ::"r"(b), "r"((uint32_t)c) : "memory");
}
__device__ __forceinline__ uint4 ld_rlx4(const uint4* p) {
  uint4 v; asm volatile("ld.relaxed.gpu.global.v4.u32 {%0, %1, %2, %3}, [%4];" : "=r"(v.x), "=r"(v.y), "=r"(v.z), "=r"(v.w) : "l"(p) : "memory"); return v;
}
__device__ __forceinline__ void st_rlx4(uint4* p, uint4 v) {
  asm volatile("st.relaxed.gpu.global.v4.u32 [%0], {%1, %2, %3, %4};" ::"l"(p), "r"(v.x), "r"(v.y), "r"(v.z), "r"(v.w) : "memory");
}
__device__ __forceinline__ void ld_rlx4_upd(uint4& v, const uint4* p, bool c) {
  asm volatile("{\n.reg .pred q;\nsetp.ne.u32 q, %5, 0;\n@q ld.relaxed.gpu.global.v4.u32 {%0, %1, %2, %3}, [%4];\n}"
               : "+r"(v.x), "+r"(v.y), "+r"(v.z), "+r"(v.w) : "l"(p), "r"((uint32_t)c) : "memory");
}
__device__ __forceinline__ uint4 ld_rlx4_if(const uint4* p, bool c) { uint4 v = make_uint4(0, 0, 0, 0); ld_rlx4_upd(v, p, c); return v; }
__device__ __forceinline__ void ld_rlx_upd(uint32_t& v, const uint32_t* p, bool c) {
  asm volatile("{\n.reg .pred q;\nsetp.ne.u32 q, %2, 0;\n@q ld.relaxed.gpu.global.u32 %0, [%1];\n}" : "+r"(v) : "l"(p), "r"((uint32_t)c) : "memory");
}
__device__ __forceinline__ uint32_t ld_rlx_if(const uint32_t* p, bool c) {
  uint32_t v = 1;
  asm volatile("{\n.reg .pred q;\nsetp.ne.u32 q, %2, 0;\n@q ld.relaxed.gpu.global.u32 %0, [%1];\n}" : "+r"(v) : "l"(p), "r"((uint32_t)c) : "memory");
  return v;
}
__device__ __forceinline__ uint32_t min4(const uint4& v) { return min(min(v.x, v.y), min(v.z, v.w)); }
__device__ __forceinline__ uint4 not4(const uint4& v) { return make_uint4(~v.x, ~v.y, ~v.z, ~v.w); }
__device__ __forceinline__ float bf_lo(uint32_t w) { return __uint_as_float(w << 16); }
__device__ __forceinline__ float bf_hi(uint32_t w) { return __uint_as_float(w & 0xFFFF0000u); }
__device__ __forceinline__ uint64_t d128(uint32_t lo) { return ((uint64_t)(64u | (1u << 30)) << 32) | lo; }
__device__ __forceinline__ uint64_t d32(uint32_t lo) { return ((uint64_t)(16u | (3u << 30)) << 32) | lo; }
__device__ __forceinline__ uint64_t dnone(uint32_t lo, uint32_t sbo16) { return ((uint64_t)sbo16 << 32) | lo; }
constexpr uint32_t LBO_K = 1u << 16, LBO_MN = 512u << 16;
__device__ __forceinline__ uint32_t phi2(float a, float b) {
  uint32_t u = pack2(a + 1.f, b + 1.f), e = pack2(ex2(a * kLog2e), ex2(b * kLog2e));
  asm("max.NaN.bf16x2 %0, %0, %1;" : "+r"(u) : "r"(0x3F803F80u));
  asm("min.NaN.bf16x2 %0, %0, %1;" : "+r"(e) : "r"(u));
  asm("fma.rn.bf16x2 %0, %0, %1, %2;" : "+r"(e) : "r"(0x3F803F80u), "r"(0x35863586u));
  return e;
}
__device__ __forceinline__ void wg_qk(float (&d)[16], uint32_t a0, uint32_t a1, uint32_t a2, uint32_t a3, uint64_t db) {
  asm volatile("wgmma.mma_async.sync.aligned.m64n32k16.f32.bf16.bf16 {%0, %1, %2, %3, %4, %5, %6, %7, %8, %9, %10, %11, %12, %13, %14, %15}, "
      "{%16, %17, %18, %19}, %20, 0, 1, 1, 0;"
      : "=f"(d[0]), "=f"(d[1]), "=f"(d[2]), "=f"(d[3]), "=f"(d[4]), "=f"(d[5]), "=f"(d[6]), "=f"(d[7]), "=f"(d[8]), "=f"(d[9]),
        "=f"(d[10]), "=f"(d[11]), "=f"(d[12]), "=f"(d[13]), "=f"(d[14]), "=f"(d[15])
      : "r"(a0), "r"(a1), "r"(a2), "r"(a3), "l"(db));
}
__device__ __forceinline__ void wg_qk16(float (&d)[8], uint32_t a0, uint32_t a1, uint32_t a2, uint32_t a3, uint64_t db) {
  asm volatile("wgmma.mma_async.sync.aligned.m64n16k16.f32.bf16.bf16 {%0, %1, %2, %3, %4, %5, %6, %7}, {%8, %9, %10, %11}, %12, 0, 1, 1, 0;"
      : "=f"(d[0]), "=f"(d[1]), "=f"(d[2]), "=f"(d[3]), "=f"(d[4]), "=f"(d[5]), "=f"(d[6]), "=f"(d[7])
      : "r"(a0), "r"(a1), "r"(a2), "r"(a3), "l"(db));
}
__device__ __forceinline__ void prefetch_l2(const void* p, int bytes) { asm volatile(ONE("cp.async.bulk.prefetch.L2.global [%0], %1;") ::"l"(p), "r"(bytes) : "memory"); }

#define BLOCK_EDGE(z) do { if (z) { const uint32_t c_ = clock32(); while (clock32() == c_) {} } } while (0)

static_assert(KVOFF == 3 * GSLOT && KVOFF == 5 * OSLOT, "slot layout");

__device__ __forceinline__ void qkv_mainloop_b(float (&acc)[96], uint32_t sb, int half, int lane) {
#pragma unroll 1
  for (int it = 0; it < 8; it++) {
    const int s = it < 5 ? it : it - 5;
    const uint32_t a16 = (sb + s * GSLOT) >> 4, la = a16 + half * 512 + LBO_K, lb = a16 + 1024 + LBO_MN;
    mbar_wait_hot(sb + BARS + 8 * (B_FULLG + s), it >= 5);
    if (threadIdx.x < 32) { TL(80 + it); if (it == 0) { TL(43); TLG(77); } }
    wg_fence();
#pragma unroll
    for (int kk = 0; kk < 4; kk++) wg_ss192<0, 1>(acc, d128(la + kk * 2), d128(lb + kk * 128), (it | kk) != 0);
    wg_commit();
    if (it > 0) {
      wg_wait<1>();
      mbar_arrive_if(sb + BARS + 8 * (B_EMPTYG + (it < 6 ? it - 1 : it - 6)), lane == 0);
    }
  }
  wg_wait<0>();
  pin(acc);
  mbar_arrive_if(sb + BARS + 8 * (B_EMPTYG + 2), lane == 0);
}
__device__ __forceinline__ void qkv_mainloop_a(float (&acc0)[96], float (&acc1)[96], uint32_t sb, int lane) {
  int s = 0, ph = 0, it = 0;
#pragma unroll 1
  for (; it < NFAST; it++) {
    const uint32_t a16 = (sb + s * GSLOT) >> 4, la = a16 + LBO_K, lb = a16 + 1024 + LBO_MN;
    mbar_wait_hot(sb + BARS + 8 * (B_FULLG + s), ph);
    if (threadIdx.x < 288) TL(88 + it);
    wg_fence();
#pragma unroll
    for (int kk = 0; kk < 4; kk++) {
      wg_ss192<0, 1>(acc0, d128(la + kk * 2), d128(lb + kk * 128), (it | kk) != 0);
      wg_ss192<0, 1>(acc1, d128(la + 512 + kk * 2), d128(lb + kk * 128), (it | kk) != 0);
    }
    wg_commit(); wg_wait<1>();
    mbar_arrive_if(sb + BARS + 8 * (B_EMPTYG + (s == 0 ? 2 : s - 1)), (lane < 3) & (it > 0));
    if (++s == 3) { s = 0; ph ^= 1; }
  }
#pragma unroll 1
  for (; it < 8; it++) {
    const uint32_t a16 = (sb + s * GSLOT) >> 4, la = a16 + LBO_K, lb = a16 + 1024 + LBO_MN;
    mbar_wait_hot(sb + BARS + 8 * (B_FULLG + s), ph);
    if (threadIdx.x < 288) TL(88 + it);
    wg_fence();
#pragma unroll
    for (int kk = 0; kk < 4; kk++) {
      wg_ss192<0, 1>(acc0, d128(la + kk * 2), d128(lb + kk * 128), 1);
      wg_commit(); wg_wait<BUSYW>();
      if (kk == (BUSYW + 1) / 2 - 1 + (BUSYW == 0)) mbar_arrive_if(sb + BARS + 8 * (B_EMPTYG + (s == 0 ? 2 : s - 1)), lane < 3);
      wg_ss192<0, 1>(acc1, d128(la + 512 + kk * 2), d128(lb + kk * 128), 1);
      wg_commit(); wg_wait<BUSYW>();
    }
    if (++s == 3) { s = 0; ph ^= 1; }
  }
  wg_wait<0>();
  pin(acc0);
  pin(acc1);
}

__device__ __forceinline__ int o_buf(int st) { return st < 5 ? st : st < 13 ? st - (st < 9 ? 5 : 4) : st == 13 ? 4 : st - 14; }
__device__ __forceinline__ void o_wait_free(uint32_t sb, int st) {
  if (st == 9) mbar_wait(sb + BARS + 8 * B_OADONE, 0);
  if (st >= 3) mbar_wait(sb + BARS + 8 * (st < 5 ? B_STGFREE : st < 9 ? B_FREEO + st - 5 : st < 13 ? B_ATTN : B_FREEO + st - 9), 0);
}

__device__ __forceinline__ uint32_t poll_flags(const uint32_t* f, uint32_t tag, uint32_t need) {
  uint32_t m;
  const uint32_t t0 = clock32();
  do { m = __ballot_sync(0xffffffffu, ld_rlx(f) == tag); } while ((m & need) != need && clock32() - t0 < (1u << 24));
  fence_async_glob();
  return m;
}

__device__ __forceinline__ void fetch_halo(uint32_t sb, int r, int j, uint32_t tag, int lane) {
  mbar_wait(sb + BARS + 8 * (B_EMPTYG + 3), 0);
  mbar_wait(sb + BARS + 8 * (B_EMPTYG + 4), 0);
  {
    const int rs = r - 1 - (lane >> 4);
    const uint32_t* w0 = reinterpret_cast<const uint32_t*>(g_ll + ((tag & 1) * 128 + max(rs, 0) * 8 + j) * 512 + (lane & 15) * 32);
    const uint32_t t0 = clock32();
    while (!__all_sync(0xffffffffu, rs < 0 || ld_rlx(w0) != 0) && clock32() - t0 < (1u << 24)) {}
    mbar_arrive_if(sb + BARS + 8 * B_LLRDY, lane == 0);
    TL(102);
  }
  const int lrs = r - 2 + (lane & 1);
  const uint32_t* f = &g_fKV[(j * 16 + max(lrs, 0)) * 2 + ((lane >> 1) & 1)];
  const uint32_t t0 = clock32();
  int nx = 0;
  while (nx < 4 && clock32() - t0 < (1u << 24)) {
    const uint32_t m = __ballot_sync(0xffffffffu, lrs < 0 || ld_rlx(f) == tag);
    if ((m >> nx) & 1u) fence_async_glob();
    for (; nx < 4 && ((m >> nx) & 1u); nx++) {
      const int blk = nx & 1, part = nx >> 1, rs = r - 2 + blk;
      if (rs < 0) continue;
      const uint32_t b = sb + BARS + 8 * (B_HALO + blk * 4 + 1 + part);
      mbar_expect(b, 8192 << part);
      bulk_load(sb + KVOFF + (blk * 4 + 1 + part) * 8192, g_kvx + (size_t)(rs * 8 + j) * 32768 + (8192 << part), 8192 << part, b);
      if (nx == 1) TL(96);
    }
  }
}

template <int Q0, int Q1>
__device__ __forceinline__ void exp_part(const float (&S)[16], uint32_t (&P)[8]) {
#pragma unroll
  for (int q = Q0; q < Q1; q++) {
    P[2 * q] = pack2(ex2(S[4 * q + 0]), ex2(S[4 * q + 1]));
    P[2 * q + 1] = pack2(ex2(S[4 * q + 2]), ex2(S[4 * q + 3]));
  }
}

__device__ __forceinline__ uint32_t attention(uint32_t sb, uint8_t* smem, uint4 q0, uint4 qc, uint4* qs, int HF, int r, int j, int w, int lane) {
  const int g = lane >> 2, t = lane & 3, row = HF * 64 + w * 16 + g;
  const float* gs = reinterpret_cast<const float*>(smem + GSOFF);
  const bool v1 = r >= 1, v0 = r >= 2;
  const float og0 = 1.f - gs[row], og1 = 1.f - gs[row + 8];
  const uint32_t dofs = (j >> 2) * 16384 + HF * 8192 + (j & 3) * 2048 + (w * 16 + g) * 32 + ((((t >> 1) ^ (g >> 2)) & 1) << 4) + (t & 1) * 8;
  const int u0 = 2 * w + (2 * t <= g), u1 = 2 * w + (2 * t + 1 <= g);
  const uint32_t kv16 = (sb + KVOFF) >> 4;
  const uint32_t z1 = v1 ? 0u : 32u << 16, z0 = v0 ? 0u : 32u << 16, vc = (((sb + ONES) >> 4) << 16) - 65535u * 256u;
  uint32_t ka = kv16 + 128 * HF + LBO_K, kb = kv16 + 1920 * HF + LBO_K;
  uint32_t va = vc - 65535u * (kv16 + 128 * HF), v45 = va + z1;
  uint32_t v67 = vc - 65535u * (kv16 + 1920 * HF) + (HF ? 0u : z1), v23 = vc - 65535u * (kv16 + 1920 * HF) + (HF ? z1 : z0);
  uint32_t badmask = 0;
  uint32_t mdv[4];
#pragma unroll
  for (int b = 0; b < 4; b++) mdv[b] = (u0 > 2 * b ? 0xFFFFu : 0u) | (u1 > 2 * b ? 0xFFFF0000u : 0u);
  pin(mdv);
  float X[16], Y[16], Xo[8], Xn[8], Yo[8], Yn[8], M[8], O[12], e[4];
  uint32_t q[4], P0[8], P1[8], P2[8], Pb[8];
#define C16(T) (((32 * (T)) >> 7) * 2048 + ((32 * (T)) & 127) * 2)
#define QK(D, K, T) wg_qk(D, q[0], q[1], q[2], q[3], d32((K) + C16(T)))
#define SETQ(V) q[0] = V.x; q[1] = V.y; q[2] = V.z; q[3] = V.w
#define PV(P, U, T, SD) do { wg_rs24<1>(O, P[0], P[1], P[2], P[3], d32((U) - 65535u * C16(T)), SD); \
                             wg_rs24<1>(O, P[4], P[5], P[6], P[7], d32((U) - 65535u * (C16(T) + 32)), 1); } while (0)
#define QK2(DO, DN, B) do { wg_qk16(DO, q[0], q[1], q[2], q[3], d32(ka + 32 * (B))); \
                            wg_qk16(DN, q[0], q[1], q[2], q[3], d32(ka + C16(8) + 32 * (B))); } while (0)
#define PV2(P, B, U) do { wg_rs24<1>(O, P[0], P[1], P[2], P[3], d32((U) + z0 - 65535u * (32 * (B))), 1); \
                          wg_rs24<1>(O, P[4], P[5], P[6], P[7], d32((U) - 65535u * (C16(8) + 32 * (B))), 1); } while (0)
#define MERGE(DO, DN, B) do { pin(DO); pin(DN); \
      M[0] = u0 > 2 * (B) ? DN[0] : DO[0]; M[1] = u1 > 2 * (B) ? DN[1] : DO[1]; M[2] = w >= (B) ? DN[2] : DO[2]; M[3] = w >= (B) ? DN[3] : DO[3]; \
      M[4] = w > (B) ? DN[4] : DO[4]; M[5] = w > (B) ? DN[5] : DO[5]; M[6] = u0 > 2 * (B) ? DN[6] : DO[6]; M[7] = u1 > 2 * (B) ? DN[7] : DO[7]; \
      pin(M); e[0] = ex2(M[0]); e[1] = ex2(M[1]); } while (0)
#define TAILM(P, B) do { wg_wait<2>(); pin(M); \
      const uint32_t md = mdv[B]; \
      const uint32_t p0 = pack2(e[0], e[1]), p1 = pack2(ex2(M[2]), ex2(M[3])), p2 = pack2(ex2(M[4]), ex2(M[5])), p3 = pack2(ex2(M[6]), ex2(M[7])); \
      P[0] = p0 & ~md; P[4] = p0 & md; P[1] = w >= (B) ? 0u : p1; P[5] = w >= (B) ? p1 : 0u; \
      P[2] = w > (B) ? 0u : p2; P[6] = w > (B) ? p2 : 0u; P[3] = p3 & ~md; P[7] = p3 & md; pin(P); } while (0)
#define FINALIZE(H, LIVE) do { \
      const float chk = ((fabsf(O[0]) + fabsf(O[1])) + (fabsf(O[2]) + fabsf(O[3]))) + ((fabsf(O[4]) + fabsf(O[5])) + (fabsf(O[6]) + fabsf(O[7]))); \
      const bool bad = !((fminf(O[8], O[10]) >= 0x1p-60f) & (fmaxf(O[8], O[10]) <= 0x1p100f) & (chk <= 0x1p126f)); \
      const bool redo = __any_sync(0xffffffffu, bad); \
      if (redo & (LIVE)) { badmask |= 1u << (H); __stcg(qs + (H) * 256, qp); } \
      STORE(H, !redo & (LIVE)); } while (0)
#define STORE(H, COND) do { const float s0 = og0 * rcp(O[8]), s1 = og1 * rcp(O[10]); \
      const uint2 o0 = make_uint2(pack2(O[0] * s0, O[1] * s0), pack2(O[4] * s0, O[5] * s0)); \
      const uint2 o1 = make_uint2(pack2(O[2] * s1, O[3] * s1), pack2(O[6] * s1, O[7] * s1)); \
      if ((H) < 3) st_pair(g_o + (r * 14 * 16384 + (H) * 32768 + dofs), o0, o1, COND); \
      else st_pair_ll(reinterpret_cast<uint8_t*>(g_o2) + (((*reinterpret_cast<volatile uint32_t*>(smem + TAGOFF) & 1) * 16 + r) * 32768 + dofs), o0, o1, COND); \
      __syncwarp(); mbar_arrive_if(sb + BARS + 8 * (B_OBDONE + (H)), (lane == 0) & (COND)); if (w == 0 && (COND)) TL(34 + HF * 4 + (H)); } while (0)
#define TLHH 3
#define TLHF 0
#define TLH(n) do { if (h == TLHH && HF == TLHF && w == 0) TL(n); } while (0)
#define HEADF(S) e[0] = ex2(S[0]); e[1] = ex2(S[1]); e[2] = ex2(S[2]); e[3] = ex2(S[3])
#define TAILF(S, P) wg_wait<2>(); pin(S); P[0] = pack2(e[0], e[1]); P[1] = pack2(e[2], e[3]); exp_part<1, 4>(S, P); pin(P)
#pragma unroll
  for (int i = 0; i < 8; i++) Pb[i] = 0;
#pragma unroll
  for (int i = 0; i < 12; i++) O[i] = 0.f;
  SETQ(q0);
  pin(O); pin(Pb); pin(q);
  wg_fence(); QK(X, kb, 6); wg_commit();
  wg_wait<0>(); pin(X);
  if (w == 0) TL(98 + HF);
  uint32_t uVp = va;
  uint4 qp = q0;
#pragma unroll 1
  for (int h = 0; h < 4; h++) {
    TLH(109);
    HEADF(X);
    wg_fence(); QK(Y, kb, 7); wg_commit(); PV2(Pb, 3, uVp); wg_commit();
    TAILF(X, P0);
    TLH(110);
    wg_wait<0>(); pin(Y); pin(O); HEADF(Y);
    wg_fence(); QK(X, ka, 4); wg_commit();
    __builtin_assume(h < 4);
    FINALIZE(h - 1, h > 0);
    TAILF(Y, P1);
    TLH(111);
    wg_wait<0>(); pin(X); HEADF(X);
    wg_fence(); QK(Y, ka, 5); wg_commit(); PV(P0, v67, 6, 0); PV(P1, v67, 7, 1); wg_commit();
    TAILF(X, P2);
    TLH(112);
    wg_wait<1>(); pin(Y); HEADF(Y);
    wg_fence(); QK(X, kb, 2); wg_commit(); PV(P2, v45, 4, 1); wg_commit();
    if (h > 0) qc = *reinterpret_cast<const uint4*>(smem + QOFF + ((h - 1) & 1) * 4096 + (HF * 128 + w * 32 + lane) * 16);
    TAILF(Y, P1);
    TLH(113);
    wg_wait<1>(); pin(X); HEADF(X);
    wg_fence(); QK(Y, kb, 3); wg_commit(); PV(P1, v45, 5, 1); wg_commit();
    TAILF(X, P0);
    TLH(114);
    wg_wait<1>(); pin(Y); HEADF(Y);
    wg_fence(); QK2(Xo, Xn, 0); wg_commit(); PV(P0, v23, 2, 1); wg_commit();
    TAILF(Y, P1);
    TLH(115);
    wg_wait<1>(); MERGE(Xo, Xn, 0);
    wg_fence(); QK2(Yo, Yn, 1); wg_commit(); PV(P1, v23, 3, 1); wg_commit();
    TAILM(P0, 0);
    wg_wait<1>(); MERGE(Yo, Yn, 1);
    wg_fence(); QK2(Xo, Xn, 2); wg_commit(); PV2(P0, 0, va); wg_commit();
    TAILM(P1, 1);
    TLH(116);
    wg_wait<1>(); MERGE(Xo, Xn, 2);
    wg_fence(); QK2(Yo, Yn, 3); wg_commit(); PV2(P1, 1, va); wg_commit();
    if (h < 2 && v1) {
      mbar_wait(sb + BARS + 8 * (B_HALO + 5) + 8 * h, 0);
      if (v0) mbar_wait(sb + BARS + 8 * (B_HALO + 1) + 8 * h, 0);
    }
    TAILM(P0, 2);
    wg_wait<1>(); MERGE(Yo, Yn, 3);
    qp = make_uint4(q[0], q[1], q[2], q[3]);
    SETQ(qc); pin(q);
    ka += 512u; kb += 512u;
    wg_fence(); QK(X, kb, 6); wg_commit();
    PV2(P0, 2, va); wg_commit();
    TAILM(Pb, 3);
    TLH(117);
    uVp = va; va -= 65535u * 512u; v45 -= 65535u * 512u; v67 -= 65535u * 512u; v23 -= 65535u * 512u;
    wg_wait<0>(); pin(X);
  }
  wg_fence(); PV2(Pb, 3, uVp); wg_commit();
  wg_wait<0>(); pin(O);
  FINALIZE(3, true);

  return badmask;
}

__device__ __forceinline__ void attention_redo(uint32_t sb, uint8_t* smem, const uint4* qs, uint32_t badmask, int HF, int r, int j, int w, int lane) {
  const int g = lane >> 2, t = lane & 3, row = HF * 64 + w * 16 + g, dbase = 2 * t - 16 * w - g;
  const float* gs = reinterpret_cast<const float*>(smem + GSOFF);
  const float og0 = 1.f - gs[row], og1 = 1.f - gs[row + 8];
  const uint32_t dofs = (j >> 2) * 16384 + HF * 8192 + (j & 3) * 2048 + (w * 16 + g) * 32 + ((((t >> 1) ^ (g >> 2)) & 1) << 4) + (t & 1) * 8;
  const uint32_t kv16 = (sb + KVOFF) >> 4;
  uint32_t uK = kv16 | LBO_K, uV = (((sb + ONES) >> 4) << 16) - 65535u * (kv16 + 256u);
  float X[16], Y[16], O[12];
  uint32_t q[4], P0[8];
#pragma unroll 1
  for (int h = 0; h < 4; h++) {
    if (bar_red_or(2 + HF, 128, (badmask >> h) & 1u)) {
      float m0 = -INFINITY, m1 = -INFINITY;
      const uint4 qc = __ldcg(qs + h * 256);
      SETQ(qc); pin(q);
#pragma unroll
      for (int i = 0; i < 12; i++) O[i] = 0.f;
      pin(O);
#pragma unroll 1
      for (int it = 0; it < 20; it++) {
        const int T = it < 10 ? it : it - 10, off = 64 * HF + 32 * T, a16 = (off >> 7) * 2048 + (off & 127) * 2;
        if (it == 10) {
          m0 = fmaxf(m0, __shfl_xor_sync(0xffffffffu, m0, 1)); m1 = fmaxf(m1, __shfl_xor_sync(0xffffffffu, m1, 1));
          m0 = fmaxf(m0, __shfl_xor_sync(0xffffffffu, m0, 2)); m1 = fmaxf(m1, __shfl_xor_sync(0xffffffffu, m1, 2));
        }
        const bool valid = (off >> 7) + r >= 2;
        wg_fence();
        wg_qk(X, q[0], q[1], q[2], q[3], d32(uK + a16));
        wg_commit(); wg_wait<0>(); pin(X);
#pragma unroll
        for (int i = 0; i < 16; i++) {
          const int d = dbase + 32 * T + 8 * (i >> 2) + (i & 1) - 8 * ((i >> 1) & 1);
          const float sc = (valid && d > 0 && d <= 256) ? X[i] : -INFINITY;
          if (it < 10) { if ((i >> 1) & 1) m1 = fmaxf(m1, sc); else m0 = fmaxf(m0, sc); }
          Y[i] = it < 10 ? -INFINITY : sc - (((i >> 1) & 1) ? m1 : m0);
        }
        exp_part<0, 4>(Y, P0);
        pin(P0);
        wg_fence();
        wg_rs24<1>(O, P0[0], P0[1], P0[2], P0[3], d32(uV - 65535u * a16), 1);
        wg_rs24<1>(O, P0[4], P0[5], P0[6], P0[7], d32(uV - 65535u * (a16 + 32)), 1);
        wg_commit(); wg_wait<0>(); pin(O);
      }
      STORE(h, ((badmask >> h) & 1u) != 0);
    }
    uK += 512u; uV -= 65535u * 512u;
  }
}

}

__global__ void __launch_bounds__(512, 1)
fused_kernel(const __grid_constant__ CUtensorMap tmX, const __grid_constant__ CUtensorMap tmWB, const __grid_constant__ CUtensorMap tmWA,
             const __grid_constant__ CUtensorMap tmWoB, const __grid_constant__ CUtensorMap tmWoA,
             const __grid_constant__ CUtensorMap tmOut, const __nv_bfloat16* __restrict__ gate_w,
             const uint8_t* pwA, const uint8_t* pwoB, const uint8_t* pwoA, uint32_t zero) {
  extern __shared__ __align__(1024) uint8_t smem[];
  const uint32_t sb = (uint32_t)__cvta_generic_to_shared(smem);
  const int tid = threadIdx.x, lane = tid & 31;
  const int warp = __shfl_sync(0xffffffffu, tid >> 5, 0);
  const int bx = blockIdx.x;
  const int r = MAP == 0 ? bx >> 3 : MAP == 2 ? 4 * ((bx >> 4) & 3) + (bx & 3) : MAP == 4 ? 2 * ((bx >> 2) & 7) + (bx & 1) : 4 * ((bx >> 3) & 3) + (bx & 3);
  const int j = MAP == 0 ? bx & 7 : MAP == 2 ? 4 * (bx >> 6) + ((bx >> 2) & 3) : MAP == 4 ? 2 * (bx >> 5) + ((bx >> 1) & 1) : 2 * (bx >> 5) + ((bx >> 2) & 1);
  auto bar = [&](int i) { return sb + BARS + 8 * i; };

  uint4 gwr = make_uint4(0, 0, 0, 0);
  if (warp == 12) {
    TL(0); TLG(62);
    if (lane == 0) {
#pragma unroll
      for (int i = 0; i < 5; i++) mbar_init(bar(B_FULLG + i), 1);
    }
    asm volatile("fence.mbarrier_init.release.cluster;" ::: "memory");
    __syncwarp();
#pragma unroll 1
    for (int i = 0; i < 5; i++) {
      mbar_expect(bar(B_FULLG + i), GSLOT);
      tma2d(sb + i * GSLOT, &tmX, bar(B_FULLG + i), i * 64, r * 128);
      tma3d(sb + i * GSLOT + 16384, &tmWB, bar(B_FULLG + i), j * 64, i * 64, 0);
    }
  }
  if (warp == 13) {
    if (lane == 0) {
#pragma unroll
      for (int i = B_EMPTYG; i < B_COUNT; i++) {
        mbar_init(bar(i), i < B_HALO ? 12 : i < B_FREEO ? 1 : i < B_OBDONE ? 4 : i <= B_ATTN ? 8 : 1);
      }
    }
    asm volatile("fence.mbarrier_init.release.cluster;" ::: "memory");
  }
  if (warp < 12) {
    if ((tid >> 6) == 4) gwr = __ldg(reinterpret_cast<const uint4*>(gate_w) + tid - 256);
    if (tid < 64) {
      const uint32_t v = tid < 32 ? 0x3F803F80u : 0u;
      *reinterpret_cast<uint4*>(smem + ONES + tid * 16) = make_uint4(v, v, v, v);
      fence_async_smem();
    }
  }
  __syncthreads();

  if (warp >= 12) {
    asm volatile("setmaxnreg.dec.sync.aligned.u32 32;");
    if (warp == 12) {
      prefetch_tm(&tmWA); prefetch_tm(&tmWoB); prefetch_tm(&tmWoA); prefetch_tm(&tmOut);
      {
        int s = 0, ph = 0;
#pragma unroll 1
        for (int idx = 5; idx < 16; idx++) {
                    const bool keepx = idx >= 8 && idx < 11;
          const int k0 = (idx < 8 ? idx : idx < 11 ? idx - 3 : idx - 11) * 64;
          mbar_wait(bar(B_EMPTYG + s), ph);
          mbar_expect(bar(B_FULLG + s), keepx ? GSLOT - 16384 : GSLOT);
          if (!keepx) tma2d(sb + s * GSLOT, &tmX, bar(B_FULLG + s), k0, r * 128);
          tma3d(sb + s * GSLOT + 16384, idx < 8 ? &tmWB : &tmWA, bar(B_FULLG + s), j * 64, k0, 0);
          mbar_arrive_if(bar(B_ISSUED), (lane == 0) & (idx == LATE));
          if (++s == 3) { s = 0; ph ^= 1; }
        }
      }
      mbar_wait(bar(B_TAG), 0);
      const uint32_t tag = *reinterpret_cast<volatile uint32_t*>(smem + TAGOFF);
      mbar_wait(bar(B_ADONE), 0);
      const uint8_t* tiles = g_o + r * 14 * 16384 + (j & 1) * 8192;
      uint32_t m = 0;
#pragma unroll
      for (int st = 0; st < 4; st++) {
        if ((m & (15u << (4 * st))) != 15u << (4 * st)) m = poll_flags(&g_fOB[r * 32 + lane], tag, 15u << (4 * st));
        o_wait_free(sb, st);
        bulk_load(sb + st * OSLOT, tiles + st * 16384, 8192, bar(B_FULLO + st));
        TL(2 + st);
      }
      uint32_t todo = 0xFF, avail = 0;
      int k = 0;
      const uint32_t t0 = clock32();
      while (todo != 0 && clock32() - t0 < (1u << 24)) {
        const uint32_t seen = __ballot_sync(0xffffffffu, ld_rlx(&g_fOA[r * 32 + (lane & 7)]) == tag);
        const int fb = (lane & 7) == 0 ? B_STGFREE : (lane & 7) < 5 ? B_FREEO + (lane & 7) - 1 : B_ATTN;
        avail = __ballot_sync(0xffffffffu, mbar_test(bar(fb), 0));
        uint32_t go = seen & avail & todo;
        if (go) fence_async_glob();
        todo &= ~go;
        while (go) {
          const int i = __ffs(go) - 1;
          go &= go - 1;
          bulk_load(sb + (i == 0 ? 4 : i < 5 ? i - 1 : i) * OSLOT, tiles + (6 + i) * 16384, 8192, bar(B_FULLO + 4) + 8 * i);
          if (lane == 0) smem[ORDOFF + k] = i | (((0x76532104u >> (4 * i)) & 15) << 4);
          __syncwarp();
          mbar_arrive_if(bar(B_SEQ) + 8 * k, lane == 0);
          TL(6 + k);
          k++;
        }
      }
      m = 0;
#pragma unroll
      for (int st = 12; st < 14; st++) {
        if ((m & (15u << (4 * (st - 8)))) != 15u << (4 * (st - 8))) m = poll_flags(&g_fOB[r * 32 + lane], tag, 15u << (4 * (st - 8)));
        o_wait_free(sb, st);
        bulk_load(sb + o_buf(st) * OSLOT, tiles + (st - 8) * 16384, 8192, bar(B_FULLO + st));
        TL(2 + st);
      }
      if (lane == 0) atomicAdd(&g_ticket, 1u);
    } else if (warp == 13) {
      mbar_wait(bar(B_FULLG), 0);
      prefetch_l2(pwA + bx * 12288, 12288);
      prefetch_l2(pwoB + bx * 4096, 4096);
      prefetch_l2(pwoA + bx * 4096, 4096);
      mbar_wait(bar(B_TAG), 0);
      const uint32_t tag = *reinterpret_cast<volatile uint32_t*>(smem + TAGOFF);
      {
        uint4* z = g_o2 + (((tag & 1) ^ 1) * 32 + r * 2) * 1024 + j * 256 + lane;
#pragma unroll 2
        for (int i = 0; i < 8; i++) z[i * 32] = make_uint4(0, 0, 0, 0);
      }
      bar_sync<1, 288>();
      if (r < 15) {
        uint8_t* dst = g_kvx + (size_t)(r * 8 + j) * 32768;
        uint32_t* f = &g_fKV[(j * 16 + r) * 2];
        bulk_store(dst + 8192, sb + KVOFF + 9 * 8192, 8192); bulk_commit();
        bulk_wait<0>(); TL(101); st_rel(f, tag); TL(100);
        mbar_wait(bar(B_ISSUED), 0);
        bulk_store(dst + 16384, sb + KVOFF + 10 * 8192, 16384); bulk_commit();
        bulk_wait<0>(); st_rel(f + 1, tag);
      }
      TL(21);
#pragma unroll 1
      for (int h = 0; h < 3; h++) {
        mbar_wait(bar(B_OBDONE + h), 0);
        st_rel(&g_fOB[r * 32 + h * 8 + j], tag);
        TL(22 + h);
      }
    } else if (warp == 14) {
      mbar_wait(bar(B_TAG), 0);
      const uint32_t tag = *reinterpret_cast<volatile uint32_t*>(smem + TAGOFF);
      uint4* z = g_ll + (((tag & 1) ^ 1) * 128 + r * 8 + j) * 512 + lane;
#pragma unroll 2
      for (int i = 0; i < 16; i++) z[i * 32] = make_uint4(0, 0, 0, 0);
      fetch_halo(sb, r, j, tag, lane);
      TL(26);
      mbar_wait(bar(B_ADONE), 0);
#pragma unroll
      for (int st = 0; st < 16; st++) {
        const int c = st < 4 ? st : st - 8;
        const uint32_t dst = sb + o_buf(st) * OSLOT + 8192;
        o_wait_free(sb, st);
        mbar_expect(bar(B_FULLO + st), st < 14 ? OSLOT : 16384);
#pragma unroll
        for (int u = 0; u < 2; u++) {
          if (st < 4 || st >= 12) tma5d(dst + u * 8192, &tmWoB, bar(B_FULLO + st), (j >> 1) * 128 + u * 64, 0, 0, 8 * (c >> 1), 4 * (c & 1));
          else tma5d(dst + u * 8192, &tmWoA, bar(B_FULLO + st), (j >> 1) * 128 + u * 64, 0, 0, 0, 4 * (st - 4));
        }
      }
    } else {
      const uint32_t tag = (ld_rlx(&g_ticket) >> 7) + 1;
      *reinterpret_cast<volatile uint32_t*>(smem + TAGOFF) = tag;
      *reinterpret_cast<volatile uint32_t*>(smem + PMASKOFF) = 0;
      __syncwarp();
      mbar_arrive_if(bar(B_TAG), lane == 0);
      uint4* z = reinterpret_cast<uint4*>(g_lp + (((tag & 1) ^ 1) * 128 + j * 16 + r) * 576);
#pragma unroll 2
      for (int i = lane; i < 144; i += 32) z[i] = make_uint4(0, 0, 0, 0);
      __syncwarp();
      {
        const uint32_t* pw = g_lp + ((tag & 1) * 128 + j * 16 + (lane & 15)) * 576 + 575;
        mbar_wait(bar(B_ADONE), 0);
        const uint32_t t0 = clock32();
        uint32_t m;
        do {
          m = __ballot_sync(0xffffffffu, ld_rlx(pw) != 0);
          *reinterpret_cast<volatile uint32_t*>(smem + PMASKOFF) = m;
        } while (m != 0xFFFFFFFFu && clock32() - t0 < (1u << 24));
        mbar_arrive_if(bar(B_PARTRDY), lane == 0);
        TL(28);
      }
      mbar_wait(bar(B_OADONE), 0);
      st_rel(&g_fOA[r * 32 + j], tag);
      TL(29);
      {
        const uint32_t* p3 = reinterpret_cast<const uint32_t*>(g_o2 + ((tag & 1) * 32 + r * 2 + (lane >> 4)) * 1024) + (j & 1) * 2048 +
                             ((lane >> 2) & 3) * 512 + (8 + 16 * (lane & 3)) * 8;
        const uint32_t t0 = clock32();
        while (!__all_sync(0xffffffffu, ld_rlx(p3) != 0) && clock32() - t0 < (1u << 24)) {}
        mbar_arrive_if(bar(B_LLO), lane == 0);
        TL(16);
      }
    }
  } else {
    const int w = warp & 3, g = lane >> 2, t = lane & 3;
    if (warp < 8) {
      const int hf = warp >> 2;
      uint4 q0, q1;
      uint4* qs = g_q + bx * 1024 + tid;
      {
        float acc[96];
        qkv_mainloop_b(acc, sb, hf, lane);
        if (warp == 0) { TL(32); TLG(74); }
        mbar_wait(bar(B_EMPTYG + 4), 0);
        mbar_wait(bar(B_TAG), 0);
        const uint32_t par = *reinterpret_cast<volatile uint32_t*>(smem + TAGOFF) & 1;
        const int key = hf * 64 + w * 16 + (lane & 15);
        const uint32_t ka = sb + KVOFF + 8 * 8192 + key * 32 + ((((lane >> 4) ^ (key >> 2)) & 1) << 4);
#pragma unroll
        for (int h = 0; h < 4; h++) {
          stsm4(ka + h * 8192, pack2(acc[32 + 8 * h], acc[33 + 8 * h]), pack2(acc[34 + 8 * h], acc[35 + 8 * h]),
                pack2(acc[36 + 8 * h], acc[37 + 8 * h]), pack2(acc[38 + 8 * h], acc[39 + 8 * h]));
          stsm4(ka + h * 8192 + 4096, pack2(acc[64 + 8 * h], acc[65 + 8 * h]), pack2(acc[66 + 8 * h], acc[67 + 8 * h]),
                pack2(acc[68 + 8 * h], acc[69 + 8 * h]), pack2(acc[70 + 8 * h], acc[71 + 8 * h]));
          if (h == 0) {
            __syncwarp();
            const int c = (hf * 64 + w * 16) * 2 + lane;
            const uint4* own = reinterpret_cast<const uint4*>(smem + KVOFF + 8 * 8192);
            uint4* dst = g_ll + (par * 128 + r * 8 + j) * 512;
            st_rlx4(dst + c, not4(own[c]));
            st_rlx4(dst + 256 + c, not4(own[256 + c]));
          }
        }
        fence_async_smem();
        asm volatile("bar.arrive 1, 288;" ::: "memory");
        if (warp == 0) TL(33);
        mbar_wait(bar(B_GATE), 0);
#pragma unroll
        for (int h = 0; h < 4; h++) {
          const float* a = acc + 8 * h;
          const uint4 v = make_uint4(pack2(a[0] * kScaleLog2, a[1] * kScaleLog2), pack2(a[2] * kScaleLog2, a[3] * kScaleLog2),
                                     pack2(a[4] * kScaleLog2, a[5] * kScaleLog2), pack2(a[6] * kScaleLog2, a[7] * kScaleLog2));
          if (h == 0) q0 = v;
          else if (h == 1) q1 = v;
          else *reinterpret_cast<uint4*>(smem + QOFF + (h - 2) * 4096 + tid * 16) = v;
        }
        mbar_wait(bar(B_EMPTYG + 3), 0);
        uint4* kv = reinterpret_cast<uint4*>(smem + KVOFF);
        if (r < 2)
          for (int c = tid; c < (2 - r) * 2048; c += 256) kv[c] = make_uint4(0, 0, 0, 0);
        if (warp == 0) TL(104);
        mbar_wait(bar(B_LLRDY), 0);
        if (warp == 0) TL(105);
        if (r >= 1) {
          const uint4* s1 = g_ll + (par * 128 + (r - 1) * 8 + j) * 512 + tid;
          const uint4* s0 = r >= 2 ? s1 - 8 * 512 : s1;
          uint4 v[4];
          const uint32_t t0 = clock32();
          do {
            v[0] = ld_rlx4(s1); v[1] = ld_rlx4(s1 + 256); v[2] = ld_rlx4(s0); v[3] = ld_rlx4(s0 + 256);
          } while (min(min(min4(v[0]), min4(v[1])), min(min4(v[2]), min4(v[3]))) == 0 && clock32() - t0 < (1u << 24));
          if (warp == 0) TL(106);
          kv[4 * 512 + tid] = not4(v[0]); kv[4 * 512 + 256 + tid] = not4(v[1]);
          if (r >= 2) { kv[tid] = not4(v[2]); kv[256 + tid] = not4(v[3]); }
        }
        fence_async_smem();
        if (warp == 0) TL(107);
        bar_sync<5, 256>();
        if (warp == 0) TL(108);
      }
      const uint32_t bad = attention(sb, smem, q0, q1, qs, hf, r, j, w, lane);
      if (bar_red_or(2 + hf, 128, bad != 0)) attention_redo(sb, smem, qs, bad, hf, r, j, w, lane);
      mbar_arrive_if(bar(B_ATTN), lane == 0);
      if (warp == 0) { TL(42); TLG(75); }
      {
        const uint4* src = g_o2 + ((*reinterpret_cast<volatile uint32_t*>(smem + TAGOFF) & 1) * 32 + r * 2 + hf) * 1024 + (j & 1) * 512 + (tid & 127);
        uint4 v[4];
        mbar_wait(bar(B_LLO), 0);
        for (int n = 0; n < 20000; n++) {
#pragma unroll
          for (int i = 0; i < 4; i++) v[i] = ld_rlx4(src + i * 128);
          if (min(min(min4(v[0]), min4(v[1])), min(min4(v[2]), min4(v[3]))) != 0) break;
        }
        if (warp == 0) TL(17);
        mbar_wait(bar(B_FREEO + 5 + hf), 0);
        uint4* dst = reinterpret_cast<uint4*>(smem + hf * OSLOT) + (tid & 127);
#pragma unroll
        for (int i = 0; i < 4; i++) dst[i * 128] = make_uint4(v[i].x ^ 0xFFFF0000u, v[i].y ^ 0xFFFF0000u, v[i].z ^ 0xFFFF0000u, v[i].w ^ 0xFFFF0000u);
        fence_async_smem();
        __syncwarp();
        mbar_arrive_if(bar(B_Q3FULL + hf), lane == 0);
      }
    } else {
      const int ta = tid - 256;
      asm volatile("setmaxnreg.inc.sync.aligned.u32 224;");
      if (ta < 64) reinterpret_cast<uint4*>(smem + GWOFF)[ta] = gwr;
      bar_sync<4, 128>();
      {
        const int rg = ta >> 3;
        float a[8];
#pragma unroll
        for (int i = 0; i < 8; i++) a[i] = 0.f;
#pragma unroll 1
        for (int it = 0; it < 8; it++) {
          const int s = it < 5 ? it : it - 5;
          const uint4 gv = reinterpret_cast<const uint4*>(smem + GWOFF)[it * 8 + (ta & 7)];
          mbar_wait(bar(B_FULLG + s), it >= 5);
          const uint8_t* xr = smem + s * GSLOT + rg * 128 + (((ta ^ rg) & 7) << 4);
          uint4 xv[8];
#pragma unroll
          for (int i = 0; i < 8; i++) xv[i] = *reinterpret_cast<const uint4*>(xr + i * 2048);
          const uint32_t dep = (xv[0].x ^ xv[1].x ^ xv[2].x) ^ (xv[3].x ^ xv[4].x ^ xv[5].x) ^ (xv[6].x ^ xv[7].x);
          mbar_arrive_if(bar(B_EMPTYG + s) + (dep & zero), lane == 0);
#pragma unroll
          for (int i = 0; i < 8; i++) {
            a[i] = fmaf(bf_lo(xv[i].x), bf_lo(gv.x), a[i]); a[i] = fmaf(bf_hi(xv[i].x), bf_hi(gv.x), a[i]);
            a[i] = fmaf(bf_lo(xv[i].y), bf_lo(gv.y), a[i]); a[i] = fmaf(bf_hi(xv[i].y), bf_hi(gv.y), a[i]);
            a[i] = fmaf(bf_lo(xv[i].z), bf_lo(gv.z), a[i]); a[i] = fmaf(bf_hi(xv[i].z), bf_hi(gv.z), a[i]);
            a[i] = fmaf(bf_lo(xv[i].w), bf_lo(gv.w), a[i]); a[i] = fmaf(bf_hi(xv[i].w), bf_hi(gv.w), a[i]);
          }
          if (w == 0) TL(120 + it);
        }
        float b4[4], b2[2];
#pragma unroll
        for (int i = 0; i < 4; i++) b4[i] = ((lane & 4) ? a[i + 4] : a[i]) + __shfl_xor_sync(0xffffffffu, (lane & 4) ? a[i] : a[i + 4], 4);
#pragma unroll
        for (int i = 0; i < 2; i++) b2[i] = ((lane & 2) ? b4[i + 2] : b4[i]) + __shfl_xor_sync(0xffffffffu, (lane & 2) ? b4[i] : b4[i + 2], 2);
        const float mine = ((lane & 1) ? b2[1] : b2[0]) + __shfl_xor_sync(0xffffffffu, (lane & 1) ? b2[0] : b2[1], 1);
        reinterpret_cast<float*>(smem + GSOFF)[rg + 16 * (ta & 7)] = __fdividef(1.f, 1.f + ex2(-mine * kLog2e));
        __syncwarp();
        mbar_arrive_if(bar(B_GATE), lane == 0);
      }
      uint32_t pq[32];
      mbar_wait(bar(B_TAG), 0);
      const uint32_t par = *reinterpret_cast<volatile uint32_t*>(smem + TAGOFF) & 1;
      uint32_t* lp = g_lp + (par * 128 + j * 16) * 576;
      {
        float acc0[96], acc1[96];
        qkv_mainloop_a(acc0, acc1, sb, lane);
        if (w == 0) { TL(64); TLG(76); }
        bar_sync<4, 128>();
        mbar_arrive_if(bar(B_ADONE), ta == 0);
        {
          float kv[32], z[4];
          const int row = w * 16 + (lane & 15);
          const uint32_t s16 = ((sb + STGOFF) >> 4) + LBO_MN;
#define KV_HALF(ACC, HALF) do { \
          _Pragma("unroll") for (int h = 0; h < 4; h++) { \
            const uint32_t a = sb + STGOFF + (HALF) * 8192 + row * 128 + (((2 * h + (lane >> 4)) ^ (row & 7)) << 4); \
            const float* k = ACC + 32 + 8 * h; \
            stsm4(a, phi2(k[0], k[1]), phi2(k[2], k[3]), phi2(k[4], k[5]), phi2(k[6], k[7])); \
            stsm4(a + 16384, pack2(k[32], k[33]), pack2(k[34], k[35]), pack2(k[36], k[37]), pack2(k[38], k[39])); } \
          fence_async_smem(); \
          bar_sync<4, 128>(); \
          BLOCK_EDGE(zero); \
          wg_fence(); \
          _Pragma("unroll") for (int kk = 4 * (HALF); kk < 4 * (HALF) + 4; kk++) { \
            wg_ss64<1, 1>(kv, d128(s16 + kk * 128), d128(s16 + 1024 + kk * 128), kk != 0); \
            wg_ss8<1, 0>(z, d128(s16 + kk * 128), dnone(((sb + ONES) >> 4) | (8u << 16), 8), kk != 0); } } while (0)
          KV_HALF(acc0, 0);
          wg_commit();
          BLOCK_EDGE(zero);
          KV_HALF(acc1, 1);
          if (w == 0) TL(66);
          wg_commit();
          BLOCK_EDGE(zero);
          wg_wait<0>(); pin(kv); pin(z);
          mbar_arrive_if(bar(B_STGFREE), lane == 0);
          uint32_t* dst = lp + r * 576;
#pragma unroll
          for (int ww = 0; ww < 4; ww++)
            if (w == ww) {
              uint32_t* p = dst + ww * 128 + g * 4 + t;
              st_rlx(p, pack2(kv[8 * ww], kv[8 * ww + 1]) ^ 0xFFFF0000u);
              st_rlx(p + 32, pack2(kv[8 * ww + 2], kv[8 * ww + 3]) ^ 0xFFFF0000u);
              st_rlx(p + 64, pack2(kv[8 * ww + 4], kv[8 * ww + 5]) ^ 0xFFFF0000u);
              st_rlx(p + 96, pack2(kv[8 * ww + 6], kv[8 * ww + 7]) ^ 0xFFFF0000u);
            }
          if (t < 2) st_rlx(dst + 512 + w * 16 + g + 8 * t, __float_as_uint(t ? z[2] : z[0]) | 0x80000000u);
        }
        if (w == 0) TL(67);
        BLOCK_EDGE(zero);
        pin(acc0); pin(acc1);
        float qb[32];
#pragma unroll
        for (int i = 0; i < 32; i++) qb[i] = acc1[i];
#pragma unroll
        for (int i = 0; i < 16; i++) pq[i] = phi2(acc0[2 * i], acc0[2 * i + 1]);
        BLOCK_EDGE(zero);
        if (w == 0) TL(68);
        uint4 v[16];
        uint32_t zv[16];
        const uint4* src = reinterpret_cast<const uint4*>(lp) + ta;
        const uint32_t* srz = lp + 512 + w * 16 + (lane & 15);
        const bool hasz = lane < 16;
        const uint32_t early = *reinterpret_cast<volatile uint32_t*>(smem + PMASKOFF);
#pragma unroll
        for (int rr = 0; rr < 16; rr++) {
          v[rr] = ld_rlx4_if(src + rr * 144, (early >> rr) & 1u);
          zv[rr] = ld_rlx_if(srz + rr * 576, hasz & ((early >> rr) & 1u));
        }
        BLOCK_EDGE(zero);
#pragma unroll
        for (int i = 0; i < 16; i++) pq[16 + i] = phi2(qb[2 * i], qb[2 * i + 1]);
        pin(pq);
        BLOCK_EDGE(zero);
        mbar_wait(bar(B_PARTRDY), 0);
#pragma unroll
        for (int rr = 0; rr < 16; rr++) {
          ld_rlx4_upd(v[rr], src + rr * 144, !((early >> rr) & 1u));
          ld_rlx_upd(zv[rr], srz + rr * 576, hasz & !((early >> rr) & 1u));
        }
        for (int n = 0; n < 20000; n++) {
          uint32_t mn = 0xFFFFFFFFu;
#pragma unroll
          for (int rr = 0; rr < 16; rr++) mn = min(min(mn, min4(v[rr])), zv[rr]);
          if (mn != 0) break;
#pragma unroll
          for (int rr = 0; rr < 16; rr++) { v[rr] = ld_rlx4(src + rr * 144); zv[rr] = ld_rlx_if(srz + rr * 576, hasz); }
        }
        if (w == 0) TL(69);
        float a[8], zs = 0.f;
#pragma unroll
        for (int i = 0; i < 8; i++) a[i] = 0.f;
#pragma unroll
        for (int rr = 0; rr < 16; rr++) {
          const uint4 u = v[rr];
          a[0] += bf_lo(u.x); a[1] += bf_hi(~u.x); a[2] += bf_lo(u.y); a[3] += bf_hi(~u.y);
          a[4] += bf_lo(u.z); a[5] += bf_hi(~u.z); a[6] += bf_lo(u.w); a[7] += bf_hi(~u.w);
          zs -= __uint_as_float(zv[rr]);
        }
        mbar_wait(bar(B_OBDONE), 0);
        uint8_t* kz = smem + KVZOFF + w * 768;
        *reinterpret_cast<uint4*>(kz + lane * 16) = make_uint4(pack2(a[0], a[1]), pack2(a[2], a[3]), pack2(a[4], a[5]), pack2(a[6], a[7]));
        if (hasz) {
          const uint32_t zz = pack2(zs, zs);
          *reinterpret_cast<uint4*>(kz + 512 + lane * 16) = make_uint4(zz, zz, zz, zz);
        }
      }
      fence_async_smem();
      bar_sync<4, 128>();
      if (w == 0) TL(70);
      {
        float D[8][12];
        wg_fence();
#pragma unroll
        for (int i = 0; i < 8; i++)
          wg_rs24<1>(D[i], pq[4 * i], pq[4 * i + 1], pq[4 * i + 2], pq[4 * i + 3], dnone((((sb + KVZOFF) >> 4) + (i & 3) * 48) | (8u << 16), 16), 0);
        wg_commit(); wg_wait<0>();
#pragma unroll
        for (int i = 0; i < 8; i++) pin(D[i]);
        const float* gs = reinterpret_cast<const float*>(smem + GSOFF);
#pragma unroll
        for (int i = 0; i < 8; i++) {
          const int row = (i >> 2) * 64 + w * 16 + g;
          const float s0 = gs[row] * rcp(D[i][8] + 1e-6f), s1 = gs[row + 8] * rcp(D[i][10] + 1e-6f);
          st_pair(g_o + (uint32_t)((r * 14 + 6 + j) * 16384 + (i >> 2) * 8192 + (i & 3) * 2048 + (w * 16 + g) * 32 + ((((t >> 1) ^ (g >> 2)) & 1) << 4) + (t & 1) * 8),
                  make_uint2(pack2(D[i][0] * s0, D[i][1] * s0), pack2(D[i][4] * s0, D[i][5] * s0)),
                  make_uint2(pack2(D[i][2] * s1, D[i][3] * s1), pack2(D[i][6] * s1, D[i][7] * s1)), true);
        }
        __syncwarp();
        mbar_arrive_if(bar(B_OADONE), lane == 0);
      }
      if (w == 0) TL(72);
      {
        float acc[64];
#pragma unroll
        for (int i = 0; i < 64; i++) acc[i] = 0.f;
        pin(acc);
#define OUT_MMA(A16, KK) wg_ss128<0, 1>(acc, d32((A16) + LBO_K + (KK) * 128), d128((A16) + 512 + LBO_MN + (KK) * 128), 1)
#pragma unroll 1
        for (int n = 0; n < 4; n++) {
          const uint32_t a16 = (sb >> 4) + n * (OSLOT >> 4);
          mbar_wait_hot(bar(B_FULLO) + 8 * n, 0);
          if (w == 0) TL(44 + n);
          wg_fence();
#pragma unroll
          for (int kk = 0; kk < 4; kk++) { OUT_MMA(a16, kk); wg_commit(); wg_wait<BUSYO>(); }
          wg_wait<0>();
          mbar_arrive_if(bar(B_FREEO) + 8 * n, lane == 0);
        }
        int n = 0;
#pragma unroll 1
        for (; n < 8; n++) {
          mbar_wait_hot(bar(B_SEQ) + 8 * n, 0);
          if (bar_red_or(4, 128, mbar_test(bar(B_ATTN), 0))) break;
          const uint32_t e = __shfl_sync(0xffffffffu, (uint32_t)*reinterpret_cast<volatile uint8_t*>(smem + ORDOFF + n), 0);
          const int i = e & 15;
          const uint32_t a16 = (sb >> 4) + (e >> 4) * (OSLOT >> 4);
          mbar_wait_hot(bar(B_FULLO + 4) + 8 * i, 0);
          if (w == 0) TL(48 + n);
          wg_fence();
#pragma unroll
          for (int kk = 0; kk < 4; kk++) { OUT_MMA(a16, kk); wg_commit(); wg_wait<BUSYO>(); }
          wg_wait<0>();
          mbar_arrive_if(bar(B_FREEO + 4) + 8 * i, (lane == 0) & (i < 3));
        }
        int pi = 8;
#pragma unroll 1
        for (; n < 8; n++) {
          mbar_wait_hot(bar(B_SEQ) + 8 * n, 0);
          const uint32_t e = __shfl_sync(0xffffffffu, (uint32_t)*reinterpret_cast<volatile uint8_t*>(smem + ORDOFF + n), 0);
          const int i = e & 15;
          const uint32_t a16 = (sb >> 4) + (e >> 4) * (OSLOT >> 4);
          mbar_wait_hot(bar(B_FULLO + 4) + 8 * i, 0);
          if (w == 0) TL(48 + n);
          wg_fence();
#pragma unroll
          for (int kk = 0; kk < 4; kk++) OUT_MMA(a16, kk);
          wg_commit(); wg_wait<1>();
          mbar_arrive_if(bar(B_FREEO + 4) + 8 * pi, (lane == 0) & (pi < 3));
          pi = i;
        }
#pragma unroll
        for (int st = 12; st < 16; st++) {
          mbar_wait_hot(bar(B_FULLO + st), 0);
          if (st >= 14) mbar_wait_hot(bar(B_Q3FULL + st - 14), 0);
          if (w == 0) TL(44 + st);
          wg_fence();
#pragma unroll
          for (int kk = 0; kk < 4; kk++) OUT_MMA((sb >> 4) + o_buf(st) * (OSLOT >> 4), kk);
          wg_commit();
          if (st == 12) { wg_wait<1>(); mbar_arrive_if(bar(B_FREEO + 4) + 8 * pi, (lane == 0) & (pi < 3)); }
        }
        wg_wait<0>(); pin(acc);
        if (w == 0) TL(60);
        const uint32_t stg = sb + 2 * OSLOT;
        const int orow = w * 16 + (lane & 15);
#pragma unroll
        for (int half = 0; half < 2; half++) {
#pragma unroll
          for (int p = 0; p < 4; p++) {
            const float* a = acc + 32 * half + 8 * p;
            stsm4(stg + half * 8192 + orow * 128 + (((2 * p + (lane >> 4)) ^ (orow & 7)) << 4), pack2(a[0], a[1]), pack2(a[2], a[3]), pack2(a[4], a[5]), pack2(a[6], a[7]));
          }
          fence_async_smem();
          bar_sync<4, 128>();
          if (w == 0) { tma2d_store(&tmOut, stg + half * 8192, (j >> 1) * 128 + half * 64, r * 128 + (j & 1) * 64); bulk_commit(); }
        }
        if (w == 0) bulk_wait_read<0>();
        if (w == 0) { TL(61); TLG(63); }
      }
    }
  }
}

typedef CUresult (*EncodeFn)(CUtensorMap*, CUtensorMapDataType, cuuint32_t, void*, const cuuint64_t*, const cuuint64_t*, const cuuint32_t*,
                             const cuuint32_t*, CUtensorMapInterleave, CUtensorMapSwizzle, CUtensorMapL2promotion, CUtensorMapFloatOOBfill);

static void make_map(EncodeFn enc, CUtensorMap* tm, const void* base, int rank, const cuuint64_t* dims, const cuuint64_t* strides, const cuuint32_t* box) {
  cuuint32_t es[5] = {1, 1, 1, 1, 1};
  enc(tm, CU_TENSOR_MAP_DATA_TYPE_BFLOAT16, rank, const_cast<void*>(base), dims, strides, box, es, CU_TENSOR_MAP_INTERLEAVE_NONE,
      CU_TENSOR_MAP_SWIZZLE_128B, CU_TENSOR_MAP_L2_PROMOTION_L2_256B, CU_TENSOR_MAP_FLOAT_OOB_FILL_NONE);
}

extern "C" void kernel_launch(void* const* d_in, const int* in_sizes, int n_in, void* d_out, int out_size) {
  (void)in_sizes; (void)n_in; (void)out_size;
  static EncodeFn enc = nullptr;
  if (!enc) {
    void* fn = nullptr;
    cudaDriverEntryPointQueryResult qr;
    cudaGetDriverEntryPoint("cuTensorMapEncodeTiled", &fn, cudaEnableDefault, &qr);
    enc = (EncodeFn)fn;
    cudaFuncSetAttribute(fused_kernel, cudaFuncAttributeMaxDynamicSharedMemorySize, SMEM_BYTES);
  }
  const void *x = d_in[0], *wA = d_in[1], *woA = d_in[2], *wB = d_in[4], *woB = d_in[5];
  CUtensorMap tmX, tmWB, tmWA, tmWoB, tmWoA, tmOut;
  { cuuint64_t d[2] = {512, 2048}, s[1] = {1024}; cuuint32_t b[2] = {64, 128};
    make_map(enc, &tmX, x, 2, d, s, b);
    cuuint32_t bh[2] = {64, 64};
    make_map(enc, &tmOut, d_out, 2, d, s, bh); }
  { cuuint64_t d[3] = {512, 512, 3}, s[2] = {3072, 1024}; cuuint32_t b[3] = {64, 64, 3};
    make_map(enc, &tmWB, wB, 3, d, s, b); make_map(enc, &tmWA, wA, 3, d, s, b); }
  { cuuint64_t d[5] = {512, 2, 2, 32, 8}, s[4] = {1024, 8192, 2048, 65536}; cuuint32_t b[5] = {64, 2, 2, 4, 4};
    make_map(enc, &tmWoB, woB, 5, d, s, b); }
  { cuuint64_t d[5] = {512, 2, 2, 4, 32}, s[4] = {1024, 8192, 2048, 16384}; cuuint32_t b[5] = {64, 2, 2, 4, 4};
    make_map(enc, &tmWoA, woA, 5, d, s, b); }
  fused_kernel<<<128, 512, SMEM_BYTES, cudaStreamPerThread>>>(tmX, tmWB, tmWA, tmWoB, tmWoA, tmOut, (const __nv_bfloat16*)d_in[6],
      (const uint8_t*)wA, (const uint8_t*)woB, (const uint8_t*)woA, 0u);
}
```
